```python
import torch

def _softmax(x, axis=-1):
    return torch.softmax(x, dim=axis)
def _gelu(x):
    return torch.nn.functional.gelu(x, approximate="tanh")
def _silu(x):
    return torch.nn.functional.silu(x)
def _sigmoid(x):
    return torch.sigmoid(x)
def _layernorm(x, axis=-1, eps=1e-5):
    m = x.mean(dim=axis, keepdim=True)
    v = x.var(dim=axis, keepdim=True, unbiased=False)
    return (x - m) / torch.sqrt(v + eps)
def _scatter_add(tgt, idx, src, axis=0):
    return tgt.clone().index_add_(axis, idx, src)
def _segment_sum(src, seg, n):
    out = torch.zeros((n,) + src.shape[1:], dtype=src.dtype)
    return out.index_add_(0, seg, src)
def _pad(x, pw):
    flat = tuple(v for pair in reversed(pw) for v in pair)
    return torch.nn.functional.pad(x, flat)

kernel_name = 'standalone__weight_only_int_quip__prompt'

def setup_inputs():

    _w = (lambda a: (lambda t: t.to(torch.bfloat16) if t.is_floating_point() else t)(torch.as_tensor(a)))
    B, S, D, F = 1, 2048, 448, 1792
    G = -1 if -1 > 0 else D
    D = (D // G) * G
    ng = D // G
    bits = 4 if 4 > 0 else 4
    qmax = 1 << bits
    qw = torch.randint(0, qmax, (D, F)).to(torch.int32)
    U, _ = (lambda *_a, **_k: torch.linalg.qr(*[torch.as_tensor(_x).float() for _x in _a], **_k))((lambda *s: torch.randn(*s, dtype=torch.bfloat16) * 0.05)(D, D))
    V, _ = (lambda *_a, **_k: torch.linalg.qr(*[torch.as_tensor(_x).float() for _x in _a], **_k))((lambda *s: torch.randn(*s, dtype=torch.bfloat16) * 0.05)(F, F))
    return {
        "x": _w((lambda *s: torch.randn(*s, dtype=torch.bfloat16) * 0.05)(B, S, D)),
        "qw": _w(qw),
        "scales": _w(torch.abs((lambda *s: torch.randn(*s, dtype=torch.bfloat16) * 0.05)(ng, F)) * 0.02 + 0.005),
        "zeros": _w(torch.full((ng, F), qmax / 2.0, dtype=float)),
        "U": _w(U.to(float)),
        "V": _w(V.to(float)),
    }

def reference(x, qw, scales, zeros, U, V):
    B, S, D = x.shape
    ng, F = scales.shape
    G = D // ng
    s = (lambda x, n, axis: torch.repeat_interleave(x, n, dim=axis))(scales, G, axis=0)
    z = (lambda x, n, axis: torch.repeat_interleave(x, n, dim=axis))(zeros, G, axis=0)
    wq = ((lambda x, dt: x.to(dt))(qw, x.dtype) - z) * s
    xr = torch.einsum("bsd,de->bse", x, U)
    h  = torch.einsum("bse,ef->bsf", xr, wq)
    y  = torch.einsum("bsf,fg->bsg", h, V)
    return y
```

```cpp
#include <cuda_runtime.h>
#include <cuda_bf16.h>
#include <cuda.h>
#include <stdint.h>

namespace quip {

constexpr int S_ = 2048, D_ = 448, F_ = 1792;
constexpr int NCTA = 112;
constexpr int SLOT = 28672;
constexpr int SPARE_OFF = 8 * SLOT, BAR_OFF = SPARE_OFF + 2048;
constexpr int SMEM_BYTES = BAR_OFF + 1024;
constexpr int B_XR = 0, B_P = 7, B_U = 35, B_T = 51, B_W = 54;
constexpr int B_R = 82;
constexpr int B_EV = 90, B_EW = 97, B_EX = 104, B_TF = 108, B_TD = 109;
constexpr uint32_t SM0 = 1024;
constexpr int NST = 9, V_OFF = NST * 14336, XS_OFF = V_OFF + NST * 8192, QS_OFF = XS_OFF + 16384 - 3584, T_OFF = 5 * SLOT;
__host__ __device__ constexpr int w_stage(int kb) { return ((kb + 8) % NST) * 14336; }
__host__ __device__ constexpr int v_stage(int kb) { return V_OFF + (kb % NST) * 8192; }
constexpr int NB_SIGA = 1, NB_SIGX = 2, NB_DQ = 3, NB_TW = 4, NB_TURN = 5, NB_EPI = 7, NB_ST = 9, NB_FREE = 11, NB_Q = 13;

#define PORD 0
#define PEER_TO(j, d) (((j) + (d)) & 3)
#define PEER_FROM(j, d) (((j) - (d)) & 3)
#define TPMAP 0x62751340u
#define TPKIND 0
#define XPOS 0xFEDCBA9876543210ull
constexpr int PF0 = 2300;
constexpr int PFD = 205;
constexpr int VLAG = 1300;
constexpr int TXP = 780;
constexpr int DX = 275;
constexpr int XLAG = 750;
constexpr int Q0 = 2600;
constexpr int QG = 1800;
constexpr int QD = 150;
constexpr int QLAG = 800;
constexpr int WLAG0 = 3750;
constexpr int WLAG1 = 4500;
#define BMODE 1
#define XF 0
constexpr int WLAG = 2800;
constexpr int XPACE = 420;
constexpr int XP1 = 30;
constexpr int XP2 = 110;
constexpr int ZPACE = 160;
constexpr int WINU = 5;
constexpr int TS0 = 800;
constexpr int TSD = 125;

#define WQ_BYTES_ (2 << 20)
#define SHIFT_ 0
constexpr int WQ_BYTES = WQ_BYTES_, XR_AT = 2 * WQ_BYTES, FLAGS_AT = XR_AT + 16 * 28 * 4096;
constexpr int FL_X = 0, FL_EPOCH = 128 * 8;
__device__ __align__(1024) uint8_t g_scratch[8 << 20];

template <int TA, int TB>
__device__ __forceinline__ void wgmma_n112(float (&d)[56], uint64_t da, uint64_t db, int scale_d) {
    asm volatile("{\n.reg .pred p;\nsetp.ne.b32 p, %58, 0;\n"
        "wgmma.mma_async.sync.aligned.m64n112k16.f32.bf16.bf16 "
        "{%0, %1, %2, %3, %4, %5, %6, %7, %8, %9, %10, %11, %12, %13, %14, %15, "
        "%16, %17, %18, %19, %20, %21, %22, %23, %24, %25, %26, %27, %28, %29, %30, %31, "
        "%32, %33, %34, %35, %36, %37, %38, %39, %40, %41, %42, %43, %44, %45, %46, %47, "
        "%48, %49, %50, %51, %52, %53, %54, %55}, "
        "%56, %57, p, 1, 1, %59, %60;\n}\n"
        : "+f"(d[0]), "+f"(d[1]), "+f"(d[2]), "+f"(d[3]), "+f"(d[4]), "+f"(d[5]), "+f"(d[6]), "+f"(d[7]),
          "+f"(d[8]), "+f"(d[9]), "+f"(d[10]), "+f"(d[11]), "+f"(d[12]), "+f"(d[13]), "+f"(d[14]), "+f"(d[15]),
          "+f"(d[16]), "+f"(d[17]), "+f"(d[18]), "+f"(d[19]), "+f"(d[20]), "+f"(d[21]), "+f"(d[22]), "+f"(d[23]),
          "+f"(d[24]), "+f"(d[25]), "+f"(d[26]), "+f"(d[27]), "+f"(d[28]), "+f"(d[29]), "+f"(d[30]), "+f"(d[31]),
          "+f"(d[32]), "+f"(d[33]), "+f"(d[34]), "+f"(d[35]), "+f"(d[36]), "+f"(d[37]), "+f"(d[38]), "+f"(d[39]),
          "+f"(d[40]), "+f"(d[41]), "+f"(d[42]), "+f"(d[43]), "+f"(d[44]), "+f"(d[45]), "+f"(d[46]), "+f"(d[47]),
          "+f"(d[48]), "+f"(d[49]), "+f"(d[50]), "+f"(d[51]), "+f"(d[52]), "+f"(d[53]), "+f"(d[54]), "+f"(d[55])
        : "l"(da), "l"(db), "r"(scale_d), "n"(TA), "n"(TB));
}

template <int TA, int TB>
__device__ __forceinline__ void wgmma_n128(float (&d)[64], uint64_t da, uint64_t db, int scale_d) {
    asm volatile("{\n.reg .pred p;\nsetp.ne.b32 p, %66, 0;\n"
        "wgmma.mma_async.sync.aligned.m64n128k16.f32.bf16.bf16 "
        "{%0, %1, %2, %3, %4, %5, %6, %7, %8, %9, %10, %11, %12, %13, %14, %15, "
        "%16, %17, %18, %19, %20, %21, %22, %23, %24, %25, %26, %27, %28, %29, %30, %31, "
        "%32, %33, %34, %35, %36, %37, %38, %39, %40, %41, %42, %43, %44, %45, %46, %47, "
        "%48, %49, %50, %51, %52, %53, %54, %55, %56, %57, %58, %59, %60, %61, %62, %63}, "
        "%64, %65, p, 1, 1, %67, %68;\n}\n"
        : "+f"(d[0]), "+f"(d[1]), "+f"(d[2]), "+f"(d[3]), "+f"(d[4]), "+f"(d[5]), "+f"(d[6]), "+f"(d[7]),
          "+f"(d[8]), "+f"(d[9]), "+f"(d[10]), "+f"(d[11]), "+f"(d[12]), "+f"(d[13]), "+f"(d[14]), "+f"(d[15]),
          "+f"(d[16]), "+f"(d[17]), "+f"(d[18]), "+f"(d[19]), "+f"(d[20]), "+f"(d[21]), "+f"(d[22]), "+f"(d[23]),
          "+f"(d[24]), "+f"(d[25]), "+f"(d[26]), "+f"(d[27]), "+f"(d[28]), "+f"(d[29]), "+f"(d[30]), "+f"(d[31]),
          "+f"(d[32]), "+f"(d[33]), "+f"(d[34]), "+f"(d[35]), "+f"(d[36]), "+f"(d[37]), "+f"(d[38]), "+f"(d[39]),
          "+f"(d[40]), "+f"(d[41]), "+f"(d[42]), "+f"(d[43]), "+f"(d[44]), "+f"(d[45]), "+f"(d[46]), "+f"(d[47]),
          "+f"(d[48]), "+f"(d[49]), "+f"(d[50]), "+f"(d[51]), "+f"(d[52]), "+f"(d[53]), "+f"(d[54]), "+f"(d[55]),
          "+f"(d[56]), "+f"(d[57]), "+f"(d[58]), "+f"(d[59]), "+f"(d[60]), "+f"(d[61]), "+f"(d[62]), "+f"(d[63])
        : "l"(da), "l"(db), "r"(scale_d), "n"(TA), "n"(TB));
}

template <int TB>
__device__ __forceinline__ void wgmma_rs_n128(float (&d)[64], uint32_t a0, uint32_t a1, uint32_t a2, uint32_t a3, uint64_t db, int scale_d) {
    asm volatile("{\n.reg .pred p;\nsetp.ne.b32 p, %69, 0;\n"
        "wgmma.mma_async.sync.aligned.m64n128k16.f32.bf16.bf16 "
        "{%0, %1, %2, %3, %4, %5, %6, %7, %8, %9, %10, %11, %12, %13, %14, %15, "
        "%16, %17, %18, %19, %20, %21, %22, %23, %24, %25, %26, %27, %28, %29, %30, %31, "
        "%32, %33, %34, %35, %36, %37, %38, %39, %40, %41, %42, %43, %44, %45, %46, %47, "
        "%48, %49, %50, %51, %52, %53, %54, %55, %56, %57, %58, %59, %60, %61, %62, %63}, "
        "{%64, %65, %66, %67}, %68, p, 1, 1, %70;\n}\n"
        : "+f"(d[0]), "+f"(d[1]), "+f"(d[2]), "+f"(d[3]), "+f"(d[4]), "+f"(d[5]), "+f"(d[6]), "+f"(d[7]),
          "+f"(d[8]), "+f"(d[9]), "+f"(d[10]), "+f"(d[11]), "+f"(d[12]), "+f"(d[13]), "+f"(d[14]), "+f"(d[15]),
          "+f"(d[16]), "+f"(d[17]), "+f"(d[18]), "+f"(d[19]), "+f"(d[20]), "+f"(d[21]), "+f"(d[22]), "+f"(d[23]),
          "+f"(d[24]), "+f"(d[25]), "+f"(d[26]), "+f"(d[27]), "+f"(d[28]), "+f"(d[29]), "+f"(d[30]), "+f"(d[31]),
          "+f"(d[32]), "+f"(d[33]), "+f"(d[34]), "+f"(d[35]), "+f"(d[36]), "+f"(d[37]), "+f"(d[38]), "+f"(d[39]),
          "+f"(d[40]), "+f"(d[41]), "+f"(d[42]), "+f"(d[43]), "+f"(d[44]), "+f"(d[45]), "+f"(d[46]), "+f"(d[47]),
          "+f"(d[48]), "+f"(d[49]), "+f"(d[50]), "+f"(d[51]), "+f"(d[52]), "+f"(d[53]), "+f"(d[54]), "+f"(d[55]),
          "+f"(d[56]), "+f"(d[57]), "+f"(d[58]), "+f"(d[59]), "+f"(d[60]), "+f"(d[61]), "+f"(d[62]), "+f"(d[63])
        : "r"(a0), "r"(a1), "r"(a2), "r"(a3), "l"(db), "r"(scale_d), "n"(TB));
}

__device__ __forceinline__ void wg_fence() { asm volatile("wgmma.fence.sync.aligned;" ::: "memory"); }
__device__ __forceinline__ void wg_commit() { asm volatile("wgmma.commit_group.sync.aligned;" ::: "memory"); }
template <int N> __device__ __forceinline__ void wg_wait() { asm volatile("wgmma.wait_group.sync.aligned %0;" ::"n"(N) : "memory"); }
template <int N> __device__ __forceinline__ void reg_fence(float (&d)[N]) {
#pragma unroll
    for (int i = 0; i < N; i++) asm volatile("" : "+f"(d[i])::"memory");
}
__device__ __forceinline__ void mbar_wait(uint32_t bar, uint32_t parity = 0) {
    asm volatile(
        "{\n.reg .pred p;\n.reg .u32 c;\nmov.u32 c, 0;\n"
        "LW:\nmbarrier.try_wait.parity.shared::cta.b64 p, [%0], %1;\n@p bra LD;\n"
        "add.u32 c, c, 1;\nsetp.lt.u32 p, c, 2000000;\n@p bra LW;\ntrap;\nLD:\n}\n" ::"r"(bar), "r"(parity) : "memory");
}
__device__ __forceinline__ bool mbar_test(uint32_t bar) {
    uint32_t ok;
    asm volatile("{\n.reg .pred p;\nmbarrier.test_wait.parity.shared::cta.b64 p, [%1], 0;\nselp.u32 %0, 1, 0, p;\n}\n" : "=r"(ok) : "r"(bar) : "memory");
    return ok;
}
__device__ __forceinline__ uint32_t mapa(uint32_t addr, uint32_t rank) {
    uint32_t r;
    asm("mapa.shared::cluster.u32 %0, %1, %2;" : "=r"(r) : "r"(addr), "r"(rank));
    return r;
}
constexpr int lr_of(int r) {
    const int t = (TPMAP >> (4 * (r >> 1))) & 7, h = (t & 1) * 2 + (r & 1);
    return TPKIND ? 4 * h + (t >> 1) : 4 * (t >> 1) + h;
}
constexpr uint64_t mk_tab(int kind) {
    uint64_t v = 0;
    for (int r = 0; r < 16; r++) {
        const int l = lr_of(r);
        v |= kind == 0 ? (uint64_t)r << (4 * l) : kind == 1 ? (uint64_t)l << (4 * r) : kind == 2 ? 1ull << (16 * (l >> 2) + r) : 1ull << (16 * (l & 3) + r);
    }
    return v;
}
constexpr uint64_t LR2R = mk_tab(0), R2LR = mk_tab(1), JMASKS = mk_tab(2), IMASKS = mk_tab(3);
__device__ __forceinline__ uint32_t rank_of(int i, int j) { return (uint32_t)(LR2R >> (16 * j + 4 * i)) & 15; }
__device__ __forceinline__ void arrive_if(bool p, uint32_t addr) {
    asm volatile("{\n.reg .pred p;\nsetp.ne.u32 p, %0, 0;\n@p mbarrier.arrive.shared::cluster.b64 _, [%1];\n}\n" ::"r"((uint32_t)p), "r"(addr) : "memory");
}
__device__ __forceinline__ bool elect() {
    uint32_t p;
    asm volatile("{\n.reg .pred p;\nelect.sync _|p, 0xffffffff;\nselp.u32 %0, 1, 0, p;\n}\n" : "=r"(p));
    return p;
}
__device__ __forceinline__ void nb_sync(int id, int n) { asm volatile("bar.sync %0, %1;" ::"r"(id), "r"(n) : "memory"); }
__device__ __forceinline__ void nb_arrive(int id, int n) { asm volatile("bar.arrive %0, %1;" ::"r"(id), "r"(n) : "memory"); }
__device__ __forceinline__ void cl_arrive() { asm volatile("barrier.cluster.arrive.relaxed.aligned;" ::: "memory"); }
__device__ __forceinline__ void cl_wait() { asm volatile("barrier.cluster.wait.aligned;" ::: "memory"); }
__device__ __forceinline__ void tma_ld_mc(uint32_t dst, const CUtensorMap* tm, uint32_t bar, int c0, int c1, uint16_t mask) {
    asm volatile("cp.async.bulk.tensor.2d.shared::cluster.global.mbarrier::complete_tx::bytes.multicast::cluster [%0], [%1, {%3, %4}], [%2], %5;"
                 ::"r"(dst), "l"(tm), "r"(bar), "r"(c0), "r"(c1), "h"(mask) : "memory");
}
__device__ __forceinline__ void wait_bulk_ld_mc(uint32_t wbar, uint32_t dst, const void* src, uint32_t bytes, uint32_t bar, uint16_t mask) {
    asm volatile(
        "{\n.reg .pred p;\n.reg .u32 c;\nmov.u32 c, 0;\n"
        "LW:\nmbarrier.try_wait.parity.shared::cta.b64 p, [%5], 0;\n@p bra LD;\n"
        "add.u32 c, c, 1;\nsetp.lt.u32 p, c, 2000000;\n@p bra LW;\ntrap;\nLD:\n"
        "elect.sync _|p, 0xffffffff;\n"
        "@p cp.async.bulk.shared::cluster.global.mbarrier::complete_tx::bytes.multicast::cluster [%0], [%1], %2, [%3], %4;\n}\n"
        ::"r"(dst), "l"(src), "r"(bytes), "r"(bar), "h"(mask), "r"(wbar) : "memory");
}
__device__ __forceinline__ void wait_tma_ld_mc(uint32_t wbar, uint32_t dst, const CUtensorMap* tm, uint32_t bar, int c0, int c1, uint16_t mask) {
    asm volatile(
        "{\n.reg .pred p;\n.reg .u32 c;\nmov.u32 c, 0;\n"
        "LW:\nmbarrier.try_wait.parity.shared::cta.b64 p, [%6], 0;\n@p bra LD;\n"
        "add.u32 c, c, 1;\nsetp.lt.u32 p, c, 2000000;\n@p bra LW;\ntrap;\nLD:\n"
        "elect.sync _|p, 0xffffffff;\n"
        "@p cp.async.bulk.tensor.2d.shared::cluster.global.mbarrier::complete_tx::bytes.multicast::cluster [%0], [%1, {%3, %4}], [%2], %5;\n}\n"
        ::"r"(dst), "l"(tm), "r"(bar), "r"(c0), "r"(c1), "h"(mask), "r"(wbar) : "memory");
}
__device__ __forceinline__ uint32_t pack2(float lo, float hi) {
    uint32_t r;
    asm("cvt.rn.bf16x2.f32 %0, %1, %2;" : "=r"(r) : "f"(hi), "f"(lo));
    return r;
}
__device__ __forceinline__ void stsm4(uint32_t a, uint32_t r0, uint32_t r1, uint32_t r2, uint32_t r3) {
    asm volatile("stmatrix.sync.aligned.m8n8.x4.shared.b16 [%0], {%1, %2, %3, %4};" ::"r"(a), "r"(r0), "r"(r1), "r"(r2), "r"(r3) : "memory");
}
__device__ __forceinline__ void stsm4t(uint32_t a, uint32_t r0, uint32_t r1, uint32_t r2, uint32_t r3) {
    asm volatile("stmatrix.sync.aligned.m8n8.x4.trans.shared.b16 [%0], {%1, %2, %3, %4};" ::"r"(a), "r"(r0), "r"(r1), "r"(r2), "r"(r3) : "memory");
}
__device__ __forceinline__ void pf_l2_if(bool p, const void* a) {
    asm volatile("{\n.reg .pred p;\nsetp.ne.u32 p, %0, 0;\n@p prefetch.global.L2 [%1];\n}\n" ::"r"((uint32_t)p), "l"(a));
}
__device__ __forceinline__ void wait_until(uint32_t t0, uint32_t dt) { while ((uint32_t)clock() - t0 < dt) {} }
__device__ __forceinline__ void tma_st(const CUtensorMap* tm, uint32_t src, int c0, int c1) {
    asm volatile("cp.async.bulk.tensor.2d.global.shared::cta.bulk_group [%0, {%2, %3}], [%1];" ::"l"(tm), "r"(src), "r"(c0), "r"(c1) : "memory");
}
__device__ __forceinline__ void fence_async_smem() { asm volatile("fence.proxy.async.shared::cta;" ::: "memory"); }

__device__ __forceinline__ uint32_t deq2(int a, int b, uint32_t z, uint32_t s) {
    uint32_t q = pack2(__int2float_rn(a), __int2float_rn(b));
    __nv_bfloat162 v = __hmul2_rn(__hsub2_rn(*reinterpret_cast<__nv_bfloat162*>(&q), *reinterpret_cast<__nv_bfloat162*>(&z)),
                                  *reinterpret_cast<__nv_bfloat162*>(&s));
    const uint32_t o = *reinterpret_cast<uint32_t*>(&v);
    return o ? o : 0x8000u;
}
struct QT { int4 q0, q1; };
struct SZ { uint2 s0, s1, z0, z1; };
__device__ __forceinline__ void q_load(QT& t, const int* q) {
    asm volatile("ld.global.nc.L1::no_allocate.v4.s32 {%0,%1,%2,%3}, [%4];" : "=r"(t.q0.x), "=r"(t.q0.y), "=r"(t.q0.z), "=r"(t.q0.w) : "l"(q));
    asm volatile("ld.global.nc.L1::no_allocate.v4.s32 {%0,%1,%2,%3}, [%4];" : "=r"(t.q1.x), "=r"(t.q1.y), "=r"(t.q1.z), "=r"(t.q1.w) : "l"(q + 32));
}
__device__ __forceinline__ void sz_load(SZ& t, const __nv_bfloat16* sp, const __nv_bfloat16* zp) {
    asm volatile("ld.global.nc.v2.u32 {%0,%1}, [%2];" : "=r"(t.s0.x), "=r"(t.s0.y) : "l"(sp));
    asm volatile("ld.global.nc.v2.u32 {%0,%1}, [%2];" : "=r"(t.s1.x), "=r"(t.s1.y) : "l"(sp + 32));
    asm volatile("ld.global.nc.v2.u32 {%0,%1}, [%2];" : "=r"(t.z0.x), "=r"(t.z0.y) : "l"(zp));
    asm volatile("ld.global.nc.v2.u32 {%0,%1}, [%2];" : "=r"(t.z1.x), "=r"(t.z1.y) : "l"(zp + 32));
}
__device__ __forceinline__ uint32_t q_off(int row, int u) { return (((u >> 1) ^ (row & 7)) << 4) + (u & 1) * 8; }
__device__ __forceinline__ void q_store(const QT& t, const SZ& p, uint32_t w) {
    asm volatile("st.shared.v2.b32 [%0], {%1,%2};" ::"r"(w), "r"(deq2(t.q0.x, t.q0.y, p.z0.x, p.s0.x)), "r"(deq2(t.q0.z, t.q0.w, p.z0.y, p.s0.y)) : "memory");
    asm volatile("st.shared.v2.b32 [%0], {%1,%2};" ::"r"(w ^ 64), "r"(deq2(t.q1.x, t.q1.y, p.z1.x, p.s1.x)), "r"(deq2(t.q1.z, t.q1.w, p.z1.y, p.s1.y)) : "memory");
}
__device__ __forceinline__ void bulk_out1(uint8_t* dst, uint32_t src, uint32_t bytes) {
    asm volatile("cp.async.bulk.global.shared::cta.bulk_group [%0], [%1], %2;" ::"l"(dst), "r"(src), "r"(bytes) : "memory");
    asm volatile("cp.async.bulk.commit_group;" ::: "memory");
}
__device__ __forceinline__ void bulk_out(uint8_t* dst, uint32_t dstep, uint32_t src, uint32_t sstep, uint32_t bytes, int n, uint32_t pace) {
    uint32_t t0 = clock();
#pragma unroll 1
    for (int q = 0; q < n; q++) {
        while ((int)((uint32_t)clock() - t0) < 0) {}
        t0 += pace;
        asm volatile("cp.async.bulk.global.shared::cta.bulk_group [%0], [%1], %2;" ::"l"(dst + q * dstep), "r"(src + q * sstep), "r"(bytes) : "memory");
    }
    asm volatile("cp.async.bulk.commit_group;" ::: "memory");
}
__device__ __forceinline__ void validate(uint32_t smb, const uint8_t* src, int first, int lane) {
    const uint32_t barb = smb + BAR_OFF, rbar = barb + (B_R + first) * 8;
    const uint32_t off = lane * 32 + (lane >> 2) * 4;
    int st = first ? 0 : 8, retries = 0;
#pragma unroll 1
    for (int kb = first; kb < 28; kb += 2) {
        const uint32_t tile = smb + st * 14336;
        mbar_wait(barb + (B_W + kb) * 8);
        while (true) {
            uint32_t v[14];
#pragma unroll
            for (int q = 0; q < 14; q++) asm volatile("ld.shared.u32 %0, [%1];" : "=r"(v[q]) : "r"(tile + off + q * 1024) : "memory");
            uint32_t m = v[0];
#pragma unroll
            for (int q = 1; q < 14; q++) m = min(m, v[q]);
            if (!__any_sync(0xffffffff, m == 0)) break;
            uint32_t bad = 0;
#pragma unroll
            for (int q = 0; q < 14; q++) bad |= (v[q] == 0) << q;
            bad = __reduce_or_sync(0xffffffff, bad);
            fence_async_smem();
            __syncwarp();
            if (lane == 0) {
                const int lo = __ffs(bad) - 1, bytes = (32 - __clz(bad) - lo) * 1024;
                asm volatile("mbarrier.arrive.expect_tx.shared::cta.b64 _, [%0], %1;" ::"r"(rbar), "r"(bytes) : "memory");
                asm volatile("cp.async.bulk.shared::cluster.global.mbarrier::complete_tx::bytes [%0], [%1], %2, [%3];"
                             ::"r"(tile + lo * 1024), "l"(src + kb * 14336 + lo * 1024), "r"(bytes), "r"(rbar) : "memory");
            }
            mbar_wait(rbar, retries & 1);
            if (++retries > 1000000) __trap();
        }
        if (lane == 0) asm volatile("mbarrier.arrive.expect_tx.shared::cta.b64 _, [%0], 8192;" ::"r"(barb + (B_P + kb) * 8) : "memory");
        st += 2;
        if (st >= NST) st -= NST;
    }
}

__device__ __forceinline__ void unit_mma(float (&acc)[64], uint32_t a_lo, uint32_t b_lo, int first, int hand) {
    const uint64_t hi = (uint64_t)(256 >> 4) << 32;
    wg_fence();
#pragma unroll
    for (int s = 0; s < 7; s++) {
        wgmma_n128<0, 1>(acc, hi | (a_lo + s * 128), hi | (b_lo + s * 256), (s > 0) | !first);
        if (s == 5 && hand >= 0) nb_arrive(hand, 256);
    }
    wg_commit();
}
__device__ __forceinline__ constexpr uint32_t desc_lo(uint32_t addr, uint32_t lbo) { return ((addr & 0x3FFFF) >> 4) | ((lbo >> 4) << 16); }
__device__ __forceinline__ uint32_t unit_slot(int u) {
    return (uint32_t)((0x4321043210743210ull >> (4 * u)) & 7) * SLOT;
}
template <int T0, int T1, int SPLIT>
__device__ __forceinline__ void out_stage(float (&acc)[64], uint32_t base, uint32_t base2) {
#pragma unroll
    for (int t = T0; t < T1; t++)
        stsm4t(t >= SPLIT ? base2 + (t - SPLIT) * 2048 : base + t * 2048, pack2(acc[8 * t], acc[8 * t + 1]), pack2(acc[8 * t + 2], acc[8 * t + 3]),
               pack2(acc[8 * t + 4], acc[8 * t + 5]), pack2(acc[8 * t + 6], acc[8 * t + 7]));
}
__device__ __forceinline__ void t_send(uint32_t smb, uint32_t barb, int i, int j, uint32_t ts0, uint32_t pace) {
    const uint32_t src = smb + T_OFF + j * 14336;
    const uint32_t p1 = rank_of(i, PEER_TO(j, 1));
    const uint32_t dst1 = mapa(src, p1), bar1 = mapa(barb + B_T * 8, p1);
    nb_sync(NB_TW, 160);
    mbar_wait(barb + B_TF * 8);
    if (elect()) {
        asm volatile("cp.async.bulk.shared::cluster.shared::cta.mbarrier::complete_tx::bytes [%0], [%1], 14336, [%2];"
                     ::"r"(dst1), "r"(src), "r"(bar1) : "memory");
        uint32_t t0 = clock() + ts0;
#pragma unroll 1
        for (int d = 2; d < 4; d++) {
            const uint32_t peer = rank_of(i, PEER_TO(j, d));
            const uint32_t dst = mapa(src, peer), bar = mapa(barb + (B_T + d - 1) * 8, peer);
#pragma unroll
            for (int q = 0; q < 7; q++) {
                while ((int)((uint32_t)clock() - t0) < 0) {}
                t0 += pace;
                asm volatile("cp.async.bulk.shared::cluster.shared::cta.mbarrier::complete_tx::bytes [%0], [%1], 2048, [%2];"
                             ::"r"(dst + q * 2048), "r"(src + q * 2048), "r"(bar) : "memory");
            }
        }
    }
    __syncwarp();
}
__device__ __forceinline__ void paced_store(const CUtensorMap* tmY, uint32_t stg, uint32_t last, int wg, int col, int row) {
    nb_sync(NB_ST + wg, 160);
    const bool el = elect();
#pragma unroll
    for (int q = 0; q < 8; q++) {
        if (el) {
            tma_st(tmY, q == 7 ? last : stg + q * 2048, col, row + q * 16);
            asm volatile("cp.async.bulk.commit_group;" ::: "memory");
            asm volatile("cp.async.bulk.wait_group.read 1;" ::: "memory");
        }
        if (q == 2 && !wg) {
            __syncwarp();
            nb_arrive(NB_FREE, 160);
        }
    }
    if (el) asm volatile("cp.async.bulk.wait_group.read 0;" ::: "memory");
    __syncwarp();
}

__device__ __forceinline__ void xu_issue(const CUtensorMap* tmX, const CUtensorMap* tmU, uint32_t smb, int r, int c, int kk, int lane,
                                         uint32_t tstart, uint32_t t_ld) {
    const int m = (r - 5 * kk) & 15;
    const int rb = (16 * c) / 7 + ((m - 7) >> 1), half = (m - 7) & 1;
    const int lo = max(7 * rb - 16 * c, 0), hi = min(7 * rb + 6 - 16 * c, 15);
    const bool isu = m < 7, act = isu || lo <= 15;
    const int pos = (int)(XPOS >> (4 * (lane & 15))) & 15;
    const uint16_t mask = (uint16_t)__ballot_sync(0xffffffff, isu ? pos % 7 == m : pos >= lo && pos <= hi);
    const int c0 = isu ? ((2 * c + m) % 7) * 64 : kk * 64, c1 = isu ? kk * 64 : rb * 128 + half * 64;
    const uint32_t dst = smb + (isu ? V_OFF + (kk + 2) * 8192 : kk * 16384 + half * 8192), bar = smb + BAR_OFF + (B_XR + kk) * 8;
    const CUtensorMap* tm = isu ? tmU : tmX;
    wait_until(tstart, t_ld);
    if (act && elect()) tma_ld_mc(dst, tm, bar, c0, c1, mask);
}
#define XU_ISSUE(kk) xu_issue(&tmX, &tmU, smb, r, c, kk, lane, tstart, TXP + (kk) * DX + XLAG)

__global__ void __cluster_dims__(16, 1, 1) __launch_bounds__(384, 1)
fused_kernel(const int* __restrict__ qw, const __nv_bfloat16* __restrict__ scales, const __nv_bfloat16* __restrict__ zeros,
             const __nv_bfloat16* __restrict__ x, const __nv_bfloat16* __restrict__ U, uint32_t* __restrict__ prog_g,
             const __nv_bfloat16* __restrict__ V, uint8_t* __restrict__ wq_g, uint8_t* __restrict__ xr_g,
             const __grid_constant__ CUtensorMap tmX, const __grid_constant__ CUtensorMap tmU,
             const __grid_constant__ CUtensorMap tmV, const __grid_constant__ CUtensorMap tmY) {
    extern __shared__ __align__(1024) uint8_t smem_raw[];
    const uint32_t tstart = clock();
    const int b = blockIdx.x;
    const int r = b & 15, c = b >> 4;
    const int lr = (int)(R2LR >> (4 * r)) & 15;
    {
        const uint32_t t = threadIdx.x;
        const uint32_t off = (28 * lr + (t >> 2)) * (F_ * 4) + c * 256 + (t & 2) * 896 + (t & 1) * 128;
        pf_l2_if(t < 112 && (BMODE == 0 || !(t & 2)), reinterpret_cast<const uint8_t*>(qw) + off);
    }
    const int lane = threadIdx.x & 31;
    const int i = lr & 3, j = lr >> 2;
    uint32_t smb = (uint32_t)__cvta_generic_to_shared(smem_raw);
    asm volatile("" : "+r"(smb));
    if (threadIdx.x >= 352) {
        const int xrow = b * 19 + lane;
        const bool isx = lane < 19;
        const bool xu_act = isx ? xrow < S_ : (lane >= 28);
        const uint8_t* xu_p = (isx ? reinterpret_cast<const uint8_t*>(x) : reinterpret_cast<const uint8_t*>(U)) +
                              (isx ? xrow * (D_ * 2) : (b * 4 + (lane & 3)) * 128);
        const int step = isx ? 128 : 64 * D_ * 2;
        wait_until(tstart, TXP);
        pf_l2_if(xu_act, xu_p);
        xu_p += step;
        cl_arrive();
        const uint8_t* vp = reinterpret_cast<const uint8_t*>(V) + b * 2048 + (lane & 15) * 128;
        const int* pq = qw + (28 * lr + lane) * F_ + (c + 14) * 64;
        int tq = max(Q0 - QLAG + c * QD, 0), nq = 0;
#pragma unroll 1
        for (int st = 1; st < 35; st++) {
            const int t = st < 7 ? TXP + st * DX : PF0 + (st - 7) * PFD;
            if (tq <= t) {
                wait_until(tstart, tq);
                pf_l2_if(lane < 28, pq);
                pf_l2_if(lane < 28, pq + 32);
                pq += 448;
                tq = ++nq < 2 ? tq + QG : 0x7fffffff;
            }
            wait_until(tstart, t);
            pf_l2_if(st < 7 ? xu_act : lane < 16, st < 7 ? xu_p : vp);
            if (st < 7) xu_p += step; else vp += 229376;
        }
        paced_store(&tmY, smb + 7 * SLOT, smb + 7 * SLOT + 14336, 1, 256 * c + 64 * i, 512 * j + 128);
        return;
    }
    const int warp = __shfl_sync(0xffffffff, threadIdx.x >> 5, 0);
    QT qa, qb;
    SZ sza;
    uint32_t epoch = 0;
    const int qcol = (c + 7 * (warp >> 2)) * 64 + (lane & 7) * 4;
    const int* qp = qw + (28 * lr + 4 * (warp & 3) + (lane >> 3)) * F_ + qcol;
    if (warp < 8) {
        q_load(qa, qp);
        if ((warp & 3) < 3) q_load(qb, qp + 16 * F_);
        sz_load(sza, scales + qcol, zeros + qcol);
    }
    if ((0x6F1 >> warp) & 1) asm volatile("ld.relaxed.gpu.global.u32 %0, [%1];" : "=r"(epoch) : "l"(prog_g + FL_EPOCH) : "memory");
    const uint32_t barb = smb + BAR_OFF;
    {
        if (elect()) {
#pragma unroll
            for (int k = 0; k < 10; k++)
                asm volatile("mbarrier.init.shared::cta.b64 [%0], %1;" ::"r"(barb + (warp * 10 + k) * 8), "r"(warp >= 9 ? 16 : 1) : "memory");
            asm volatile("fence.mbarrier_init.release.cluster;" ::: "memory");
        }
        __syncwarp();
        const int k = warp * 10 + lane;
        const uint32_t bytes = k < B_P ? 24576 : (k < B_T ? SLOT : 14336);
        asm volatile("{\n.reg .pred p;\nsetp.ne.u32 p, %2, 0;\n@p mbarrier.arrive.expect_tx.shared::cta.b64 _, [%0], %1;\n}\n"
                     ::"r"(barb + k * 8), "r"(bytes), "r"((uint32_t)(lane < 10 && k < B_R && (k < B_P || k >= B_U))) : "memory");
    }
    cl_arrive();

    if (warp < 8) {
        const int wg = warp >> 2, w = warp & 3;
        const int k8 = lane & 7;
        uint8_t* const wdst = wq_g + (j * 28 + c) * 14336 + i * 3584;
        {
            const int row = 4 * w + (lane >> 3);
            const uint32_t src = smb + (wg ? QS_OFF + 3584 : XS_OFF), w0 = src + row * 128 + q_off(28 * i + row, k8);
            q_store(qa, sza, w0);
            if (w < 3) q_store(qb, sza, w0 + 2048);
            fence_async_smem();
            if (wg) nb_sync(NB_EPI + 1, 128); else nb_sync(NB_SIGA, 192);
            if (warp == 0 || warp == 6) {
                if (lane == 0) bulk_out1(wdst + (epoch & 1) * WQ_BYTES + wg * 7 * 14336, src, 3584);
                __syncwarp();
            }
        }
        if (warp == 4) {
            const int xt = 16 * c + ((int)(XPOS >> (4 * r)) & 15), rb = xt / 7, cb = xt - rb * 7;
            const uint32_t zsrc = smb + QS_OFF + 3 * 3584;
            const bool early = (0x60380E03u >> ((rb >> 2) * 8 + cb)) & 1;
            if (lane < 8) asm volatile("st.relaxed.gpu.global.u32 [%0], %1;" ::"l"(prog_g + FL_X + xt * 8 + lane), "r"(epoch) : "memory");
#pragma unroll
            for (int k = 0; k < 7; k++) asm volatile("st.shared.v4.b32 [%0], {%1,%1,%1,%1};" ::"r"(zsrc + k * 512 + lane * 16), "r"(0) : "memory");
            fence_async_smem();
            cl_wait();
            nb_sync(NB_SIGX, 160);
            if (lane == 0) {
                bulk_out(xr_g + rb * (28 * 4096) + cb * 16384, 2048, smb + XS_OFF, 2048, 2048, 8, XPACE + (early ? (rb & 3) * XP1 : XP2));
                asm volatile("cp.async.bulk.wait_group 0;" ::: "memory");
            }
            __syncwarp();
            if (lane < 8) {
                asm volatile("fence.proxy.async;" ::: "memory");
                asm volatile("st.relaxed.gpu.global.u32 [%0], %1;" ::"l"(prog_g + FL_X + xt * 8 + lane), "r"(epoch + 1) : "memory");
            }
            __syncwarp();
            if (lane == 0) {
                bulk_out(wq_g + ((epoch & 1) ^ 1) * WQ_BYTES + b * 14336, 3584, zsrc, 0, 3584, 4, ZPACE);
                asm volatile("cp.async.bulk.wait_group.read 0;" ::: "memory");
            }
            __syncwarp();
            nb_arrive(NB_DQ, 224);
        } else if (warp == 5 || warp == 6) {
            const int row = 4 * (w - 1) + (lane >> 3);
            const int* q1 = qw + (28 * lr + row) * F_ + c * 64 + k8 * 4;
            const uint32_t soff = row * 128 + q_off(28 * i + row, k8);
            uint8_t* dst = wdst + (epoch & 1) * WQ_BYTES;
            SZ sz[2];
#pragma unroll
            for (int g = 2; g < 4; g++) sz_load(sz[g - 2], scales + (c + 7 * g) * 64 + k8 * 4, zeros + (c + 7 * g) * 64 + k8 * 4);
            cl_wait();
#pragma unroll
            for (int g = 2; g < 4; g++) {
                const uint32_t src = smb + QS_OFF + (2 - (g & 1)) * 3584;
                QT t[4];
                wait_until(tstart, Q0 + (g - 2) * QG + c * QD);
#pragma unroll
                for (int k = 0; k < 4; k++)
                    if (k < 3 || w == 1) q_load(t[k], q1 + g * 448 + k * 8 * F_);
#pragma unroll
                for (int k = 0; k < 4; k++)
                    if (k < 3 || w == 1) q_store(t[k], sz[g - 2], src + soff + k * 1024);
                fence_async_smem();
                if (w == 2 && lane == 0) asm volatile("cp.async.bulk.wait_group.read 0;" ::: "memory");
                nb_sync(NB_Q, 64);
                if (w == 2 && lane == 0) bulk_out1(dst + g * 7 * 14336, src, 3584);
            }
            if (lane == 0) asm volatile("cp.async.bulk.wait_group.read 0;" ::: "memory");
            __syncwarp();
            nb_arrive(NB_DQ, 224);
        } else if (warp == 7) {
            const uint8_t* src = wq_g + (epoch & 1) * WQ_BYTES + j * 28 * 14336;
            cl_wait();
            validate(smb, src, 1, lane);
        }
        const int pw = wg;
        int nu = lane < 5 ? lane + 6 : lane + 5;
        uint32_t tr = mapa(barb + (B_EX + ((nu >> 2) & 3)) * 8, rank_of(nu & 3, j));
        uint32_t stg_lane = ((lane >> 4) * 8 + (lane & 7)) * 128 + (((2 * w + ((lane >> 3) & 1)) ^ (lane & 7)) << 4);
        asm volatile("" : "+r"(tr), "+r"(stg_lane));
        float accA[64], accB[64];

        if (wg == 0) {
            const int xkb = (lane & 7) + 1;
            const int xtrig = lane < 8 ? (lane ? xkb - 2 : 99) : (lane < 16 ? min(xkb - 1, 6) : 99);
            const uint32_t xa = lane < 8 ? mapa(barb + (B_EV + (xkb >> 2)) * 8, rank_of(i, xkb & 3))
                                         : mapa(barb + (B_EW + (xkb >> 2)) * 8, rank_of(xkb & 3, j));
            const int nkb = lane + NST;
            uint32_t ta;
            int la;
            if (lane < 19) {
                ta = mapa(barb + (B_EV + (nkb >> 2)) * 8, rank_of(i, nkb & 3));
                la = lane;
            } else if (lane < 25) {
                const int u = lane - 19;
                ta = mapa(barb + (B_EX + (u >> 2)) * 8, rank_of(u & 3, j));
                la = 16 + ((0xABA864 >> (4 * u)) & 15);
            } else {
                ta = mapa(barb + B_TF * 8, rank_of(i, lane & 3));
                la = lane >= 28 ? 26 : 99;
            }
            const uint32_t tb = mapa(barb + (B_EW + ((nkb >> 2) & 7)) * 8, rank_of(nkb & 3, j));
            uint32_t tw = smb + T_OFF + j * 14336 + (2 * w + ((lane >> 3) & 1)) * 256 + (lane >> 4) * 128 + (lane & 7) * 16;
            uint32_t xw = smb + XS_OFF + w * 4096 + lane * 16;
            asm volatile("" : "+r"(tw), "+r"(xw));
            const uint64_t hi = (uint64_t)((1024 >> 4) | (1u << 30)) << 32;
            constexpr uint32_t a_lo = desc_lo(SM0, 1024), b_lo = desc_lo(SM0, 16);

            float xacc[64];
            cl_wait();
            mbar_wait(barb + B_XR * 8);
#pragma unroll
            for (int kk = 0; kk < 7; kk++) {
                wg_fence();
#pragma unroll
                for (int k = 0; k < 4; k++)
                    wgmma_n128<1, 0>(xacc, hi | (a_lo + (v_stage(kk + 2) >> 4) + k * 128), hi | (b_lo + kk * 1024 + k * 2), (kk | k) != 0);
                wg_commit();
                if (kk > 0) {
                    wg_wait<1>();
                    arrive_if(xtrig == kk - 1, xa);
                }
                if (kk < 6) {
                    mbar_wait(barb + (B_XR + kk + 1) * 8);
                } else {
                    if (threadIdx.x == 0) asm volatile("cp.async.bulk.wait_group.read 0;" ::: "memory");
                    nb_sync(NB_EPI, 128);
                }
            }
            const bool p0 = mbar_test(barb + B_P * 8);
            wg_wait<0>();
            reg_fence(xacc);
            arrive_if(xtrig == 6, xa);
#pragma unroll
            for (int t = 0; t < 8; t++)
                stsm4(xw + t * 512, pack2(xacc[8 * t], xacc[8 * t + 1]), pack2(xacc[8 * t + 2], xacc[8 * t + 3]),
                      pack2(xacc[8 * t + 4], xacc[8 * t + 5]), pack2(xacc[8 * t + 6], xacc[8 * t + 7]));
            if (!XF) {
                fence_async_smem();
                nb_arrive(NB_SIGX, 160);
            }

            float acc[56];
            if (!p0) mbar_wait(barb + B_P * 8);
#pragma unroll
            for (int kb = 0; kb < 28; kb++) {
                wg_fence();
#pragma unroll
                for (int k = 0; k < 4; k++) wgmma_n112<1, 0>(acc, hi | (a_lo + (v_stage(kb) >> 4) + k * 128), hi | (b_lo + (w_stage(kb) >> 4) + k * 2), (kb | k) != 0);
                wg_commit();
                if (kb < 27) {
                    const bool ready = mbar_test(barb + (B_P + kb + 1) * 8);
                    if (XF && kb == 0) {
                        fence_async_smem();
                        nb_arrive(NB_SIGX, 160);
                    }
                    if (kb >= 1) {
                        wg_wait<1>();
                        arrive_if(la == kb - 1, ta);
                        if (kb < 20) arrive_if(lane == kb - 1, tb);
                    }
                    if (!ready) mbar_wait(barb + (B_P + kb + 1) * 8);
                }
            }
            wg_wait<1>();
            nb_sync(NB_DQ, 224);
            arrive_if(la == 26, ta);
            const bool u0 = mbar_test(barb + B_U * 8);
            wg_wait<0>();
            reg_fence(acc);
            arrive_if(la == 27, ta);
            uint32_t tp[28];
#pragma unroll
            for (int n = 0; n < 28; n++) tp[n] = pack2(acc[2 * n], acc[2 * n + 1]);
#pragma unroll
            for (int s = 0; s < 7; s++) stsm4(tw + s * 2048, tp[4 * s], tp[4 * s + 1], tp[4 * s + 2], tp[4 * s + 3]);
            if (!u0) mbar_wait(barb + B_U * 8);
            wg_fence();
#pragma unroll
            for (int s = 0; s < 7; s++) {
                wgmma_rs_n128<1>(accA, tp[4 * s], tp[4 * s + 1], tp[4 * s + 2], tp[4 * s + 3],
                                 ((uint64_t)(256 >> 4) << 32) | (desc_lo(SM0, 128) + s * 256), s > 0);
                if (s == 1) {
                    fence_async_smem();
                    nb_arrive(NB_TW, 160);
                }
                if (s == 5) nb_arrive(NB_TURN + 1, 256);
            }
            wg_commit();
            wg_wait<0>();
        }

        {
            constexpr uint32_t tlo = desc_lo(SM0 + T_OFF, 128), slo = desc_lo(SM0, 128);
            const uint32_t a0 = tlo + j * 896, a1 = tlo + PEER_FROM(j, 1) * 896, a2 = tlo + PEER_FROM(j, 2) * 896, a3 = tlo + PEER_FROM(j, 3) * 896;
            const int col = 256 * c + 64 * i, row = 512 * j + 128 * pw;
            const int me = NB_TURN + pw, other = NB_TURN + (pw ^ 1);
            int u;
            u = pw;
            if (pw) {
                mbar_wait(barb + (B_U + 1) * 8);
                nb_sync(me, 256);
                unit_mma(accA, a0, slo + (unit_slot(1) >> 4), 1, other);
                wg_wait<0>();
            }
            arrive_if(lane == u, tr);
            u = 2 + pw;
            mbar_wait(barb + (B_U + u) * 8);
            nb_sync(me, 256);
            unit_mma(accB, a0, slo + (unit_slot(u) >> 4), 1, other);
            wg_wait<0>();
            arrive_if(lane == u, tr);
            u = 4 + pw;
            mbar_wait(barb + (B_U + u) * 8);
            mbar_wait(barb + (B_T + 0) * 8);
            nb_sync(me, 256);
            unit_mma(accA, a1, slo + (unit_slot(u) >> 4), 0, other);
            wg_wait<0>();
            arrive_if(lane == 4 && !pw, tr);
            u = 7 + 2 * pw;
            mbar_wait(barb + (B_U + u) * 8);
            if (!pw) {
                mbar_wait(barb + (B_U + 6) * 8);
                nb_sync(me, 256);
                unit_mma(accB, a1, slo + (unit_slot(6) >> 4), 0, -1);
            }
            mbar_wait(barb + (B_T + 1) * 8);
            if (pw) {
                mbar_wait(barb + (B_T + 2) * 8);
                mbar_wait(barb + (B_U + 10) * 8);
                nb_sync(me, 256);
            }
            unit_mma(accA, a2, slo + (unit_slot(u) >> 4), 0, -1);
            u++;
            if (!pw) {
                mbar_wait(barb + (B_U + 8) * 8);
                wg_wait<1>();
                arrive_if(lane == 6, tr);
                mbar_wait(barb + (B_T + 2) * 8);
            }
            unit_mma(accA, a3, slo + (unit_slot(u) >> 4), 0, other);
            wg_wait<1>();
            arrive_if(lane == u - 1, tr);
            if (!pw) mbar_wait(barb + B_TD * 8);
            wg_wait<0>();
            reg_fence(accA);
            arrive_if(lane == u, tr);
            const uint32_t stg = pw ? smb + 7 * SLOT : smb + T_OFF + j * 14336, stg7 = pw ? stg + 14336 : smb + SPARE_OFF;
            out_stage<0, 8, 7>(accA, stg + stg_lane, stg7 + stg_lane);
            u = 11 + 2 * pw;
            const bool r0 = mbar_test(barb + (B_U + u) * 8), r1 = mbar_test(barb + (B_U + u + 1) * 8);
            fence_async_smem();
            nb_arrive(NB_ST + pw, 160);
            if (!r0) mbar_wait(barb + (B_U + u) * 8);
            if (!r1) mbar_wait(barb + (B_U + u + 1) * 8);
            nb_sync(me, 256);
            if (pw) {
                unit_mma(accB, a1, slo + (unit_slot(13) >> 4), 0, -1);
                u++;
            }
            unit_mma(accB, a2, slo + (unit_slot(u) >> 4), 0, -1);
            u++;
            if (pw) mbar_wait(barb + (B_U + 15) * 8);
            unit_mma(accB, a3, slo + (unit_slot(u) >> 4), 0, pw ? -1 : other);
            const uint32_t sb = pw ? smb + unit_slot(14) : smb + 7 * SLOT + 16384, sb6 = pw ? sb + 12288 : stg;
            if (pw) { wg_wait<1>(); nb_sync(NB_EPI + wg, 128); } else nb_sync(NB_FREE, 160);
            wg_wait<0>();
            reg_fence(accB);
#define OUT_STEP(t0, t1)                                                                              \
    out_stage<t0, t1, 6>(accB, sb + stg_lane, sb6 + stg_lane);                                        \
    fence_async_smem();                                                                               \
    nb_sync(NB_EPI + wg, 128);                                                                        \
    if (w < (t1) - (t0) && elect()) {                                                                 \
        const int t = (t0) + w;                                                                       \
        tma_st(&tmY, t >= 6 ? sb6 + (t - 6) * 2048 : sb + t * 2048, col, row + 256 + t * 16);         \
    }                                                                                                 \
    __syncwarp();
            OUT_STEP(0, 1)
            OUT_STEP(1, 4)
            OUT_STEP(4, 8)
            if (elect()) {
                asm volatile("cp.async.bulk.commit_group;" ::: "memory");
                asm volatile("cp.async.bulk.wait_group.read 0;" ::: "memory");
            }
            __syncwarp();
        }
    } else if (warp == 8) {
        cl_wait();
#pragma unroll 1
        for (int kk = 0; kk < 7; kk++) XU_ISSUE(kk);
        const uint16_t vmask = (uint16_t)(IMASKS >> (16 * i));
#pragma unroll 1
        for (int n = 0; n < 7; n++) {
            const int kb = 4 * n + j;
            const uint32_t dst = smb + v_stage(kb), bar = barb + (B_P + kb) * 8;
            wait_until(tstart, PF0 + kb * PFD + VLAG);
            wait_tma_ld_mc(barb + (kb > 1 ? B_EV + n : B_XR + kb) * 8, dst, &tmV, bar, 256 * c + 64 * i, 64 * kb, vmask);
        }
        t_send(smb, barb, i, j, TS0, TSD);
#pragma unroll
        for (int d = 0; d < 3; d++) mbar_wait(barb + (B_T + d) * 8);
        arrive_if(lane < 16, mapa(barb + B_TD * 8, rank_of(i, lane & 3)));
    } else if (warp == 9) {
        const uint8_t* wsrc = wq_g + (__shfl_sync(0xffffffff, epoch, 0) & 1) * WQ_BYTES + j * 28 * 14336;
        nb_arrive(NB_SIGA, 192);
        cl_wait();
        const uint16_t jmask = (uint16_t)(JMASKS >> (16 * j));
#pragma unroll 1
        for (int n = 0; n < 7; n++) {
            const int kb = 4 * n + i;
            const uint32_t dst = smb + w_stage(kb);
            wait_until(tstart, kb < 7 ? WLAG0 : kb < 14 ? WLAG1 : WLAG + Q0 + (kb / 7 - 2) * QG + (kb % 7) * QD);
            wait_bulk_ld_mc(barb + (kb ? B_EW + n : B_XR) * 8, dst, wsrc + kb * 14336, 14336, barb + (B_W + kb) * 8, jmask);
        }
        const uint32_t* pp = prog_g + FL_X + (28 * j + min(lane, 27)) * 8;
        const bool first = (((0x60380E03u >> (j * 8)) & 0x7F) << (7 * i) >> lane) & 1;
        uint32_t v = epoch;
#pragma unroll 1
        for (int n = 0; n < 4; n++) {
            int u = 4 * n + i;
            int ch = (int)((0x3332211002103210ull >> (4 * u)) & 3);
            int p = (int)((0x3213232321110000ull >> (4 * u)) & 3);
            const uint8_t* src = xr_g + (4 * j + ch) * (28 * 4096) + PEER_FROM(j, p) * SLOT;
            const uint32_t dst = smb + unit_slot(u);
            if (n < 2) {
                int spin = 0;
                while (__any_sync(0xffffffff, v != epoch + 1 && (n || first))) {
                    if (v != epoch + 1 && (n || first)) asm volatile("ld.acquire.gpu.global.u32 %0, [%1];" : "=r"(v) : "l"(pp) : "memory");
                    if (++spin > 4000000) __trap();
                }
                asm volatile("fence.proxy.async.global;" ::: "memory");
            }
            mbar_wait(barb + (B_U + u - WINU) * 8);
            wait_bulk_ld_mc(barb + (B_EX + n) * 8, dst, src, SLOT, barb + (B_U + u) * 8, jmask);
        }
    } else {
        if ((smb & 0xFFFFFF) != SM0) __trap();
        const uint8_t* src = wq_g + (epoch & 1) * WQ_BYTES + j * 28 * 14336;
        asm volatile("" : "+l"(src));
        nb_arrive(NB_SIGA, 192);
        cl_wait();
        validate(smb, src, 0, lane);
        paced_store(&tmY, smb + T_OFF + j * 14336, smb + SPARE_OFF, 0, 256 * c + 64 * i, 512 * j);
        if (b == 0 && lane == 0) asm volatile("st.relaxed.gpu.global.u32 [%0], %1;" ::"l"(prog_g + FL_EPOCH), "r"(epoch + 1) : "memory");
    }
}

__global__ void fb_dequant(const int* __restrict__ qw, const __nv_bfloat16* __restrict__ scales, const __nv_bfloat16* __restrict__ zeros,
                           __nv_bfloat16* __restrict__ w) {
    const int idx = blockIdx.x * blockDim.x + threadIdx.x, f = idx % F_;
    w[idx] = __hmul_rn(__hsub_rn(__float2bfloat16_rn(__int2float_rn(qw[idx])), zeros[f]), scales[f]);
}
__global__ void __launch_bounds__(256) fb_gemm(const __nv_bfloat16* __restrict__ A, const __nv_bfloat16* __restrict__ B,
                                               __nv_bfloat16* __restrict__ C, int N, int K) {
    __shared__ float sa[16][65], sb[16][64];
    const int tx = threadIdx.x & 15, ty = threadIdx.x >> 4, m0 = blockIdx.y * 64, n0 = blockIdx.x * 64;
    float acc[4][4] = {};
    for (int k0 = 0; k0 < K; k0 += 16) {
        for (int e = threadIdx.x; e < 1024; e += 256) {
            sa[e & 15][e >> 4] = __bfloat162float(A[(m0 + (e >> 4)) * K + k0 + (e & 15)]);
            sb[e >> 6][e & 63] = __bfloat162float(B[(k0 + (e >> 6)) * N + n0 + (e & 63)]);
        }
        __syncthreads();
#pragma unroll
        for (int k = 0; k < 16; k++)
#pragma unroll
            for (int p = 0; p < 4; p++)
#pragma unroll
                for (int q = 0; q < 4; q++) acc[p][q] += sa[k][ty * 4 + p] * sb[k][tx + 16 * q];
        __syncthreads();
    }
    for (int p = 0; p < 4; p++)
        for (int q = 0; q < 4; q++) C[(m0 + ty * 4 + p) * N + n0 + tx + 16 * q] = __float2bfloat16_rn(acc[p][q]);
}

typedef CUresult (*EncodeFn)(CUtensorMap*, CUtensorMapDataType, cuuint32_t, void*, const cuuint64_t*, const cuuint64_t*,
                             const cuuint32_t*, const cuuint32_t*, CUtensorMapInterleave, CUtensorMapSwizzle,
                             CUtensorMapL2promotion, CUtensorMapFloatOOBfill);

static void make_map(EncodeFn enc, CUtensorMap* tm, const void* p, int cols, int rows, int bc, int br) {
    cuuint64_t gd[2] = {(cuuint64_t)cols, (cuuint64_t)rows};
    cuuint64_t gs[1] = {(cuuint64_t)cols * 2};
    cuuint32_t bd[2] = {(cuuint32_t)bc, (cuuint32_t)br};
    cuuint32_t es[2] = {1, 1};
    enc(tm, CU_TENSOR_MAP_DATA_TYPE_BFLOAT16, 2, const_cast<void*>(p), gd, gs, bd, es, CU_TENSOR_MAP_INTERLEAVE_NONE,
        CU_TENSOR_MAP_SWIZZLE_128B, CU_TENSOR_MAP_L2_PROMOTION_L2_128B, CU_TENSOR_MAP_FLOAT_OOB_FILL_NONE);
}

}

extern "C" void kernel_launch(void* const* d_in, const int* in_sizes, int n_in, void* d_out, int out_size) {
    using namespace quip;
    const __nv_bfloat16* x = (const __nv_bfloat16*)d_in[0];
    const int* qw = (const int*)d_in[1];
    const __nv_bfloat16* scales = (const __nv_bfloat16*)d_in[2];
    const __nv_bfloat16* zeros = (const __nv_bfloat16*)d_in[3];
    const __nv_bfloat16* U = (const __nv_bfloat16*)d_in[4];
    const __nv_bfloat16* V = (const __nv_bfloat16*)d_in[5];

    cudaLaunchConfig_t cfg = {};
    cfg.gridDim = NCTA;
    cfg.blockDim = 384;
    cfg.dynamicSmemBytes = SMEM_BYTES;
    cfg.stream = cudaStreamPerThread;

    static bool init = false;
    static EncodeFn enc = nullptr;
    static void *p_wq, *p_xr, *p_prog;
    static bool fused_ok = false;
    if (!init) {
        init = true;
        cudaGetSymbolAddress(&p_wq, g_scratch);
        p_wq = (void*)((((uintptr_t)p_wq + (2 << 20) - 1) & ~(uintptr_t)((2 << 20) - 1)) + SHIFT_);
        p_xr = (uint8_t*)p_wq + XR_AT;
        p_prog = (uint8_t*)p_wq + FLAGS_AT;
        void* fn = nullptr;
        cudaDriverEntryPointQueryResult st;
        cudaGetDriverEntryPoint("cuTensorMapEncodeTiled", &fn, cudaEnableDefault, &st);
        enc = (EncodeFn)fn;
        cudaFuncSetAttribute(fused_kernel, cudaFuncAttributeMaxDynamicSharedMemorySize, SMEM_BYTES);
        cudaFuncSetAttribute(fused_kernel, cudaFuncAttributeNonPortableClusterSizeAllowed, 1);
        int nclusters = 0;
        fused_ok = enc && cudaOccupancyMaxActiveClusters(&nclusters, fused_kernel, &cfg) == cudaSuccess && nclusters >= NCTA / 16;
        (void)cudaGetLastError();
    }
    if (!fused_ok) {
        __nv_bfloat16 *w = (__nv_bfloat16*)p_wq, *t = w + D_ * F_, *xr = (__nv_bfloat16*)p_xr;
        fb_dequant<<<D_ * F_ / 256, 256, 0, cfg.stream>>>(qw, scales, zeros, w);
        fb_gemm<<<dim3(D_ / 64, S_ / 64), 256, 0, cfg.stream>>>(x, U, xr, D_, D_);
        fb_gemm<<<dim3(F_ / 64, D_ / 64), 256, 0, cfg.stream>>>(w, V, t, F_, F_);
        fb_gemm<<<dim3(F_ / 64, S_ / 64), 256, 0, cfg.stream>>>(xr, t, (__nv_bfloat16*)d_out, F_, D_);
        return;
    }
    CUtensorMap tmX, tmU, tmV, tmY;
    make_map(enc, &tmX, x, D_, S_, 64, 64);
    make_map(enc, &tmU, U, D_, D_, 64, 64);
    make_map(enc, &tmV, V, F_, F_, 64, 64);
    make_map(enc, &tmY, d_out, F_, S_, 64, 16);
    cudaLaunchKernelEx(&cfg, fused_kernel, qw, scales, zeros, x, U, (uint32_t*)p_prog, V, (uint8_t*)p_wq, (uint8_t*)p_xr,
                       tmX, tmU, tmV, tmY);
}
```
